```python
import torch

def _softmax(x, axis=-1):
    return torch.softmax(x, dim=axis)
def _gelu(x):
    return torch.nn.functional.gelu(x, approximate="tanh")
def _silu(x):
    return torch.nn.functional.silu(x)
def _sigmoid(x):
    return torch.sigmoid(x)
def _layernorm(x, axis=-1, eps=1e-5):
    m = x.mean(dim=axis, keepdim=True)
    v = x.var(dim=axis, keepdim=True, unbiased=False)
    return (x - m) / torch.sqrt(v + eps)
def _scatter_add(tgt, idx, src, axis=0):
    return tgt.clone().index_add_(axis, idx, src)
def _segment_sum(src, seg, n):
    out = torch.zeros((n,) + src.shape[1:], dtype=src.dtype)
    return out.index_add_(0, seg, src)
def _pad(x, pw):
    flat = tuple(v for pair in reversed(pw) for v in pair)
    return torch.nn.functional.pad(x, flat)

kernel_name = 'gated_mix__sliding_local_dilated__spectral_fnet__prompt'

def setup_inputs():

    _w = (lambda a: (lambda t: t.to(torch.bfloat16) if t.is_floating_point() else t)(torch.as_tensor(a)))
    def _A_setup():
        B, S, D = 1, 2048, 1024
        return {
            "x": _w((lambda *s: torch.randn(*s, dtype=torch.bfloat16) * 0.05)(B, S, D)),
            "wqkv": _w((lambda *s: torch.randn(*s, dtype=torch.bfloat16) * 1.6)(D, 3 * D)),
            "wo": _w((lambda *s: torch.randn(*s, dtype=torch.bfloat16) * 0.2)(D, D)),
        }
    _A_in = _A_setup()

    def _B_setup():
        B, S, D = 1, 2048, 1024
        ns = torch.arange(S)[:, None] * torch.arange(S)[None, :]
        nd = torch.arange(D)[:, None] * torch.arange(D)[None, :]
        Ws_re = torch.cos(-2.0 * torch.pi * ns / S).to(float)
        Ws_im = torch.sin(-2.0 * torch.pi * ns / S).to(float)
        Wd_re = torch.cos(-2.0 * torch.pi * nd / D).to(float)
        Wd_im = torch.sin(-2.0 * torch.pi * nd / D).to(float)
        return {
            "x": _w((lambda *s: torch.randn(*s, dtype=torch.bfloat16) * 0.05)(B, S, D)),
            "dft_seq_re": _w(Ws_re),
            "dft_seq_im": _w(Ws_im),
            "dft_hid_re": _w(Wd_re),
            "dft_hid_im": _w(Wd_im),
        }
    _B_in = _B_setup()

    return {
        "A_x": _A_in["x"],
        "A_wqkv": _A_in["wqkv"],
        "A_wo": _A_in["wo"],
        "B_x": _B_in["x"],
        "B_dft_seq_re": _B_in["dft_seq_re"],
        "B_dft_seq_im": _B_in["dft_seq_im"],
        "B_dft_hid_re": _B_in["dft_hid_re"],
        "B_dft_hid_im": _B_in["dft_hid_im"],
        "gate_w": _w((lambda *s: torch.randn(*s, dtype=torch.bfloat16) * 0.05)(1024) * 16.0),
    }

def reference(A_x, A_wqkv, A_wo, B_x, B_dft_seq_re, B_dft_seq_im, B_dft_hid_re, B_dft_hid_im, gate_w):
    def _A_ref(x, wqkv, wo):
        B, S, D = x.shape
        H = 32; Dh = D // H
        W, dil = 8, 2
        qkv = (lambda x, *d: x.permute(*d))((x @ wqkv).reshape(B, S, 3, H, Dh), 2, 0, 3, 1, 4)
        q, k, v = qkv[0], qkv[1], qkv[2]
        scale = Dh ** -0.5
        pos = torch.arange(S)
        off = torch.arange(W) * dil
        idx = pos[:, None] - off[None, :]
        mask = idx >= 0
        idx_c = torch.where(mask, idx, 0).reshape(-1)
        kg = k[:, :, idx_c, :].reshape(B, H, S, W, Dh)
        vg = v[:, :, idx_c, :].reshape(B, H, S, W, Dh)
        logits = torch.einsum("bhsd,bhswd->bhsw", q, kg) * scale
        logits = torch.where(mask[None, None, :, :], logits, -1e9)
        attn = _softmax(logits, axis=-1)
        o = torch.einsum("bhsw,bhswd->bhsd", attn, vg)
        return (lambda x, *d: x.permute(*d))(o, 0, 2, 1, 3).reshape(B, S, D) @ wo

    def _B_ref(x, dft_seq_re, dft_seq_im, dft_hid_re, dft_hid_im):
        a = torch.einsum("bsd,ed->bse", x, dft_hid_re)
        b = torch.einsum("bsd,ed->bse", x, dft_hid_im)
        y = torch.einsum("ts,bse->bte", dft_seq_re, a) - torch.einsum("ts,bse->bte", dft_seq_im, b)
        return y

    x = A_x
    g = _sigmoid((x * gate_w).sum(-1, keepdims=True))
    a = _A_ref(x, A_wqkv, A_wo)
    b = _B_ref(x, B_dft_seq_re, B_dft_seq_im, B_dft_hid_re, B_dft_hid_im)
    return g * a + (1 - g) * b
```

```cpp
#include <cuda_runtime.h>
#include <cuda_bf16.h>
#include <cuda.h>
#include <stdint.h>

namespace {

constexpr int SLOT = 57344;
constexpr int NSLOT = 4;
constexpr int SPARE_OFF = 49152;
constexpr int SM_BAR = NSLOT * SLOT;
constexpr int BAR_FULL = 0, BAR_EMPTY = 32, BAR_HFREE = 64, BAR_QDONE = 72, BAR_GATE = 80, BAR_HREADY = 88, BAR_OREADY = 96, BAR_HSTAGED = 104  , BAR_STAGED = 120  , BAR_HXREADY = 184;
constexpr int SM_GATE = SM_BAR + 256;
constexpr int SMEM_BYTES = SM_GATE + 1024 + 1024;
constexpr int HN = 232;
constexpr int KB_Q0 = 16, KB_S0 = 32, KB_O0 = 64, KB_ALL = 72;

constexpr int CONS_REGS = 224;
constexpr int AUX_REGS = 56;
constexpr int LAG_H = 2;
constexpr int LAG_Q = 1;
constexpr int LAG_S = 2;
constexpr int LAG_F = 4;
constexpr int CATCH_Q = 2;
constexpr int PF_DIST = 8;
constexpr int ZERO_PACE = 100;
constexpr int HST_PACE = 500;
constexpr int START_GAP = 700;
constexpr int HPD = 5;

__host__ __device__ constexpr int slot_of(int i) { return i < 12 ? (i & 3) : i < 32 ? (i - 12) % 3 : (0x4B >> (2 * (i & 3))) & 3; }
__host__ __device__ constexpr int par_of(int i) { return i < 12 ? (i >> 2) & 1 : i < 32 ? (3 + (i - 12) / 3) & 1 : (((i & 3) < 2 ? 1 : 0) ^ ((i >> 2) & 1)); }

constexpr uint64_t slot_tab(int i0) { uint64_t t = 0; for (int j = 0; j < 32; j++) t |= (uint64_t)slot_of(i0 + j) << (2 * j); return t; }
constexpr uint32_t par_tab(int i0) { uint32_t t = 0; for (int j = 0; j < 32; j++) t |= (uint32_t)par_of(i0 + j) << j; return t; }
constexpr uint64_t SLOT_TAB = slot_tab(0), SLOT_TAB_F = slot_tab(32);
constexpr uint32_t PAR_TAB = par_tab(0), PAR_TAB_F = par_tab(32);

struct Maps { CUtensorMap xH, xX, hre, him, xQ, wqkv, sre, sim, ab, abst, o, wo, out; };

constexpr int CNT_GATE = 0;
constexpr int CNT_O = 8;
constexpr int CNT_H = 24;
constexpr int CNT_HALO = 32;
constexpr int CNT_Z = 160;
constexpr int CNT_HX = 224;
constexpr int CNT_N = 232;

__device__ __align__(1024) uint4 g_halo[128 * 2 * 2 * 2 * 32];
__device__ __align__(1024) __nv_bfloat16 g_ab[2048 * 2048];
__device__ __align__(1024) __nv_bfloat16 g_o[2048 * 1024];
__device__ __align__(16) float g_gate[2048];
__device__ unsigned g_cnt[CNT_N * 32];
__device__ unsigned g_epoch[128 * 4];

__device__ __forceinline__ uint32_t smem_u32(const void* p) { return (uint32_t)__cvta_generic_to_shared(p); }
__device__ __forceinline__ void mbar_init(uint32_t bar, uint32_t cnt) { asm volatile("mbarrier.init.shared::cta.b64 [%0], %1;" ::"r"(bar), "r"(cnt) : "memory"); }
__device__ __forceinline__ void mbar_expect_tx(uint32_t bar, uint32_t bytes) { asm volatile("mbarrier.arrive.expect_tx.shared::cta.b64 _, [%0], %1;" ::"r"(bar), "r"(bytes) : "memory"); }
__device__ __forceinline__ void mbar_arrive(uint32_t bar) { asm volatile("mbarrier.arrive.shared::cta.b64 _, [%0];" ::"r"(bar) : "memory"); }
__device__ __forceinline__ bool mbar_try_wait(uint32_t bar, uint32_t parity) {
  uint32_t ok;
  asm volatile("{\n.reg .pred p;\nmbarrier.try_wait.parity.shared::cta.b64 p, [%1], %2;\nselp.u32 %0, 1, 0, p;\n}\n" : "=r"(ok) : "r"(bar), "r"(parity) : "memory");
  return ok;
}
__device__ __forceinline__ void mbar_wait(uint32_t bar, uint32_t parity) {
  uint32_t it = 0;
#pragma unroll 1
  while (!mbar_try_wait(bar, parity)) { if (++it > (1u << 15)) break; }
}
__device__ __forceinline__ void cnt_wait(const unsigned* p, unsigned target) {
  uint32_t it = 0;
  while (true) {
    unsigned v;
    asm volatile("ld.acquire.gpu.global.u32 %0, [%1];" : "=r"(v) : "l"(p) : "memory");
    if ((int)(v - target) >= 0) break;
    if (++it > (1u << 20)) break;
    __nanosleep(64);
  }
}
__device__ __forceinline__ void cnt_signal(unsigned* p) {
  asm volatile("fence.acq_rel.gpu;\nred.relaxed.gpu.global.add.u32 [%0], 1;" ::"l"(p) : "memory");
}
__device__ __forceinline__ void fence_async_all() { asm volatile("fence.proxy.async;" ::: "memory"); }
__device__ __forceinline__ void fence_async_smem() { asm volatile("fence.proxy.async.shared::cta;" ::: "memory"); }
__device__ __forceinline__ void tma_load_2d(uint32_t dst, const void* map, uint32_t bar, int c0, int c1) {
  asm volatile("cp.async.bulk.tensor.2d.shared::cluster.global.mbarrier::complete_tx::bytes [%0], [%1, {%3, %4}], [%2];"
               ::"r"(dst), "l"(map), "r"(bar), "r"(c0), "r"(c1) : "memory");
}
__device__ __forceinline__ void tma_load_3d(uint32_t dst, const void* map, uint32_t bar, int c0, int c1, int c2) {
  asm volatile("cp.async.bulk.tensor.3d.shared::cluster.global.mbarrier::complete_tx::bytes [%0], [%1, {%3, %4, %5}], [%2];"
               ::"r"(dst), "l"(map), "r"(bar), "r"(c0), "r"(c1), "r"(c2) : "memory");
}
__device__ __forceinline__ void tma_load_4d(uint32_t dst, const void* map, uint32_t bar, int c0, int c1, int c2, int c3) {
  asm volatile("cp.async.bulk.tensor.4d.shared::cluster.global.mbarrier::complete_tx::bytes [%0], [%1, {%3, %4, %5, %6}], [%2];"
               ::"r"(dst), "l"(map), "r"(bar), "r"(c0), "r"(c1), "r"(c2), "r"(c3) : "memory");
}
__device__ __forceinline__ void tma_prefetch_4d(const void* map, int c0, int c1, int c2, int c3) {
  asm volatile("cp.async.bulk.prefetch.tensor.4d.L2.global [%0, {%1, %2, %3, %4}];" ::"l"(map), "r"(c0), "r"(c1), "r"(c2), "r"(c3) : "memory");
}
__device__ __forceinline__ void tma_load_5d(uint32_t dst, const void* map, uint32_t bar, int c0, int c1, int c2, int c3, int c4) {
  asm volatile("cp.async.bulk.tensor.5d.shared::cluster.global.mbarrier::complete_tx::bytes [%0], [%1, {%3, %4, %5, %6, %7}], [%2];"
               ::"r"(dst), "l"(map), "r"(bar), "r"(c0), "r"(c1), "r"(c2), "r"(c3), "r"(c4) : "memory");
}
__device__ __forceinline__ uint4 ldg_cg_v4(const void* p) {
  uint4 v; asm volatile("ld.global.cg.v4.u32 {%0,%1,%2,%3}, [%4];" : "=r"(v.x), "=r"(v.y), "=r"(v.z), "=r"(v.w) : "l"(p) : "memory"); return v;
}
__device__ __forceinline__ void tma_store_2d(const void* map, uint32_t src, int c0, int c1) {
  asm volatile("cp.async.bulk.tensor.2d.global.shared::cta.bulk_group [%0, {%2, %3}], [%1];" ::"l"(map), "r"(src), "r"(c0), "r"(c1) : "memory");
}
__device__ __forceinline__ void tma_load_2d_h(uint32_t dst, const void* map, uint32_t bar, int c0, int c1, uint64_t pol) {
  asm volatile("cp.async.bulk.tensor.2d.shared::cluster.global.mbarrier::complete_tx::bytes.L2::cache_hint [%0], [%1, {%3, %4}], [%2], %5;"
               ::"r"(dst), "l"(map), "r"(bar), "r"(c0), "r"(c1), "l"(pol) : "memory");
}
__device__ __forceinline__ void bulk_commit() { asm volatile("cp.async.bulk.commit_group;" ::: "memory"); }
template <int N> __device__ __forceinline__ void bulk_wait_read() { asm volatile("cp.async.bulk.wait_group.read %0;" ::"n"(N) : "memory"); }
template <int N> __device__ __forceinline__ void bulk_wait() { asm volatile("cp.async.bulk.wait_group %0;" ::"n"(N) : "memory"); }
__device__ __forceinline__ void prefetch_map(const void* map) { asm volatile("prefetch.tensormap [%0];" ::"l"(map) : "memory"); }
__device__ __forceinline__ void wgmma_fence() { asm volatile("wgmma.fence.sync.aligned;" ::: "memory"); }
__device__ __forceinline__ void wgmma_commit() { asm volatile("wgmma.commit_group.sync.aligned;" ::: "memory"); }
template <int N> __device__ __forceinline__ void wgmma_wait() { asm volatile("wgmma.wait_group.sync.aligned %0;" ::"n"(N) : "memory"); }
template <int LEN> __device__ __forceinline__ void fence_acc(float (&a)[LEN]) {
#pragma unroll
  for (int i = 0; i < LEN; i++) asm volatile("" : "+f"(a[i])::"memory");
}
__device__ __forceinline__ void bar_sync(int id, int n) { asm volatile("bar.sync %0, %1;" ::"r"(id), "r"(n) : "memory"); }
__device__ __forceinline__ void bar_arrive(int id, int n) { asm volatile("bar.arrive %0, %1;" ::"r"(id), "r"(n) : "memory"); }
__device__ __forceinline__ uint64_t make_desc(uint32_t d16, uint32_t off, uint32_t lbo_bytes) {
  return (uint64_t)(d16 + ((off >> 4) | ((lbo_bytes >> 4) << 16))) | (0x40000040ull << 32);
}
__device__ __forceinline__ uint32_t pack2(float lo, float hi) {
  uint32_t r; asm("cvt.rn.bf16x2.f32 %0, %1, %2;" : "=r"(r) : "f"(hi), "f"(lo)); return r;
}
__device__ __forceinline__ float bf_lo(uint32_t v) { return __uint_as_float(v << 16); }
__device__ __forceinline__ float bf_hi(uint32_t v) { return __uint_as_float(v & 0xFFFF0000u); }
__device__ __forceinline__ void stmatrix_x4(uint32_t addr, uint32_t a, uint32_t b, uint32_t c, uint32_t d) {
  asm volatile("stmatrix.sync.aligned.m8n8.x4.shared.b16 [%0], {%1, %2, %3, %4};" ::"r"(addr), "r"(a), "r"(b), "r"(c), "r"(d) : "memory");
}
__device__ __forceinline__ float ex2(float x) { float r; asm("ex2.approx.ftz.f32 %0, %1;" : "=f"(r) : "f"(x)); return r; }

template <int TB, int OFF = 0, int LEN>
__device__ __forceinline__ void wgmma_n256(float (&d)[LEN], uint64_t da, uint64_t db, int scale_d) {
  asm volatile(
      "{\n.reg .pred p;\nsetp.ne.b32 p, %130, 0;\n"
      "wgmma.mma_async.sync.aligned.m64n256k16.f32.bf16.bf16 "
      "{%0, %1, %2, %3, %4, %5, %6, %7, %8, %9, %10, %11, %12, %13, %14, %15, %16, %17, %18, %19, %20, %21, %22, %23, %24, %25, %26, %27, %28, %29, %30, %31, %32, %33, %34, %35, %36, %37, %38, %39, %40, %41, %42, %43, %44, %45, %46, %47, %48, %49, %50, %51, %52, %53, %54, %55, %56, %57, %58, %59, %60, %61, %62, %63, %64, %65, %66, %67, %68, %69, %70, %71, %72, %73, %74, %75, %76, %77, %78, %79, %80, %81, %82, %83, %84, %85, %86, %87, %88, %89, %90, %91, %92, %93, %94, %95, %96, %97, %98, %99, %100, %101, %102, %103, %104, %105, %106, %107, %108, %109, %110, %111, %112, %113, %114, %115, %116, %117, %118, %119, %120, %121, %122, %123, %124, %125, %126, %127}, "
      "%128, %129, p, 1, 1, 0, %131;\n}\n"
      : "+f"(d[OFF + 0]), "+f"(d[OFF + 1]), "+f"(d[OFF + 2]), "+f"(d[OFF + 3]), "+f"(d[OFF + 4]), "+f"(d[OFF + 5]), "+f"(d[OFF + 6]), "+f"(d[OFF + 7]), "+f"(d[OFF + 8]), "+f"(d[OFF + 9]), "+f"(d[OFF + 10]), "+f"(d[OFF + 11]), "+f"(d[OFF + 12]), "+f"(d[OFF + 13]), "+f"(d[OFF + 14]), "+f"(d[OFF + 15]), "+f"(d[OFF + 16]), "+f"(d[OFF + 17]), "+f"(d[OFF + 18]), "+f"(d[OFF + 19]), "+f"(d[OFF + 20]), "+f"(d[OFF + 21]), "+f"(d[OFF + 22]), "+f"(d[OFF + 23]), "+f"(d[OFF + 24]), "+f"(d[OFF + 25]), "+f"(d[OFF + 26]), "+f"(d[OFF + 27]), "+f"(d[OFF + 28]), "+f"(d[OFF + 29]), "+f"(d[OFF + 30]), "+f"(d[OFF + 31]), "+f"(d[OFF + 32]), "+f"(d[OFF + 33]), "+f"(d[OFF + 34]), "+f"(d[OFF + 35]), "+f"(d[OFF + 36]), "+f"(d[OFF + 37]), "+f"(d[OFF + 38]), "+f"(d[OFF + 39]), "+f"(d[OFF + 40]), "+f"(d[OFF + 41]), "+f"(d[OFF + 42]), "+f"(d[OFF + 43]), "+f"(d[OFF + 44]), "+f"(d[OFF + 45]), "+f"(d[OFF + 46]), "+f"(d[OFF + 47]), "+f"(d[OFF + 48]), "+f"(d[OFF + 49]), "+f"(d[OFF + 50]), "+f"(d[OFF + 51]), "+f"(d[OFF + 52]), "+f"(d[OFF + 53]), "+f"(d[OFF + 54]), "+f"(d[OFF + 55]), "+f"(d[OFF + 56]), "+f"(d[OFF + 57]), "+f"(d[OFF + 58]), "+f"(d[OFF + 59]), "+f"(d[OFF + 60]), "+f"(d[OFF + 61]), "+f"(d[OFF + 62]), "+f"(d[OFF + 63]), "+f"(d[OFF + 64]), "+f"(d[OFF + 65]), "+f"(d[OFF + 66]), "+f"(d[OFF + 67]), "+f"(d[OFF + 68]), "+f"(d[OFF + 69]), "+f"(d[OFF + 70]), "+f"(d[OFF + 71]), "+f"(d[OFF + 72]), "+f"(d[OFF + 73]), "+f"(d[OFF + 74]), "+f"(d[OFF + 75]), "+f"(d[OFF + 76]), "+f"(d[OFF + 77]), "+f"(d[OFF + 78]), "+f"(d[OFF + 79]), "+f"(d[OFF + 80]), "+f"(d[OFF + 81]), "+f"(d[OFF + 82]), "+f"(d[OFF + 83]), "+f"(d[OFF + 84]), "+f"(d[OFF + 85]), "+f"(d[OFF + 86]), "+f"(d[OFF + 87]), "+f"(d[OFF + 88]), "+f"(d[OFF + 89]), "+f"(d[OFF + 90]), "+f"(d[OFF + 91]), "+f"(d[OFF + 92]), "+f"(d[OFF + 93]), "+f"(d[OFF + 94]), "+f"(d[OFF + 95]), "+f"(d[OFF + 96]), "+f"(d[OFF + 97]), "+f"(d[OFF + 98]), "+f"(d[OFF + 99]), "+f"(d[OFF + 100]), "+f"(d[OFF + 101]), "+f"(d[OFF + 102]), "+f"(d[OFF + 103]), "+f"(d[OFF + 104]), "+f"(d[OFF + 105]), "+f"(d[OFF + 106]), "+f"(d[OFF + 107]), "+f"(d[OFF + 108]), "+f"(d[OFF + 109]), "+f"(d[OFF + 110]), "+f"(d[OFF + 111]), "+f"(d[OFF + 112]), "+f"(d[OFF + 113]), "+f"(d[OFF + 114]), "+f"(d[OFF + 115]), "+f"(d[OFF + 116]), "+f"(d[OFF + 117]), "+f"(d[OFF + 118]), "+f"(d[OFF + 119]), "+f"(d[OFF + 120]), "+f"(d[OFF + 121]), "+f"(d[OFF + 122]), "+f"(d[OFF + 123]), "+f"(d[OFF + 124]), "+f"(d[OFF + 125]), "+f"(d[OFF + 126]), "+f"(d[OFF + 127])
      : "l"(da), "l"(db), "r"(scale_d), "n"(TB));
}

template <int TB, int OFF = 0, int LEN>
__device__ __forceinline__ void wgmma_n232(float (&d)[LEN], uint64_t da, uint64_t db, int scale_d) {
  asm volatile(
      "{\n.reg .pred p;\nsetp.ne.b32 p, %118, 0;\n"
      "wgmma.mma_async.sync.aligned.m64n232k16.f32.bf16.bf16 "
      "{%0, %1, %2, %3, %4, %5, %6, %7, %8, %9, %10, %11, %12, %13, %14, %15, %16, %17, %18, %19, %20, %21, %22, %23, %24, %25, %26, %27, %28, %29, %30, %31, %32, %33, %34, %35, %36, %37, %38, %39, %40, %41, %42, %43, %44, %45, %46, %47, %48, %49, %50, %51, %52, %53, %54, %55, %56, %57, %58, %59, %60, %61, %62, %63, %64, %65, %66, %67, %68, %69, %70, %71, %72, %73, %74, %75, %76, %77, %78, %79, %80, %81, %82, %83, %84, %85, %86, %87, %88, %89, %90, %91, %92, %93, %94, %95, %96, %97, %98, %99, %100, %101, %102, %103, %104, %105, %106, %107, %108, %109, %110, %111, %112, %113, %114, %115}, "
      "%116, %117, p, 1, 1, 0, %119;\n}\n"
      : "+f"(d[OFF + 0]), "+f"(d[OFF + 1]), "+f"(d[OFF + 2]), "+f"(d[OFF + 3]), "+f"(d[OFF + 4]), "+f"(d[OFF + 5]), "+f"(d[OFF + 6]), "+f"(d[OFF + 7]), "+f"(d[OFF + 8]), "+f"(d[OFF + 9]), "+f"(d[OFF + 10]), "+f"(d[OFF + 11]), "+f"(d[OFF + 12]), "+f"(d[OFF + 13]), "+f"(d[OFF + 14]), "+f"(d[OFF + 15]), "+f"(d[OFF + 16]), "+f"(d[OFF + 17]), "+f"(d[OFF + 18]), "+f"(d[OFF + 19]), "+f"(d[OFF + 20]), "+f"(d[OFF + 21]), "+f"(d[OFF + 22]), "+f"(d[OFF + 23]), "+f"(d[OFF + 24]), "+f"(d[OFF + 25]), "+f"(d[OFF + 26]), "+f"(d[OFF + 27]), "+f"(d[OFF + 28]), "+f"(d[OFF + 29]), "+f"(d[OFF + 30]), "+f"(d[OFF + 31]), "+f"(d[OFF + 32]), "+f"(d[OFF + 33]), "+f"(d[OFF + 34]), "+f"(d[OFF + 35]), "+f"(d[OFF + 36]), "+f"(d[OFF + 37]), "+f"(d[OFF + 38]), "+f"(d[OFF + 39]), "+f"(d[OFF + 40]), "+f"(d[OFF + 41]), "+f"(d[OFF + 42]), "+f"(d[OFF + 43]), "+f"(d[OFF + 44]), "+f"(d[OFF + 45]), "+f"(d[OFF + 46]), "+f"(d[OFF + 47]), "+f"(d[OFF + 48]), "+f"(d[OFF + 49]), "+f"(d[OFF + 50]), "+f"(d[OFF + 51]), "+f"(d[OFF + 52]), "+f"(d[OFF + 53]), "+f"(d[OFF + 54]), "+f"(d[OFF + 55]), "+f"(d[OFF + 56]), "+f"(d[OFF + 57]), "+f"(d[OFF + 58]), "+f"(d[OFF + 59]), "+f"(d[OFF + 60]), "+f"(d[OFF + 61]), "+f"(d[OFF + 62]), "+f"(d[OFF + 63]), "+f"(d[OFF + 64]), "+f"(d[OFF + 65]), "+f"(d[OFF + 66]), "+f"(d[OFF + 67]), "+f"(d[OFF + 68]), "+f"(d[OFF + 69]), "+f"(d[OFF + 70]), "+f"(d[OFF + 71]), "+f"(d[OFF + 72]), "+f"(d[OFF + 73]), "+f"(d[OFF + 74]), "+f"(d[OFF + 75]), "+f"(d[OFF + 76]), "+f"(d[OFF + 77]), "+f"(d[OFF + 78]), "+f"(d[OFF + 79]), "+f"(d[OFF + 80]), "+f"(d[OFF + 81]), "+f"(d[OFF + 82]), "+f"(d[OFF + 83]), "+f"(d[OFF + 84]), "+f"(d[OFF + 85]), "+f"(d[OFF + 86]), "+f"(d[OFF + 87]), "+f"(d[OFF + 88]), "+f"(d[OFF + 89]), "+f"(d[OFF + 90]), "+f"(d[OFF + 91]), "+f"(d[OFF + 92]), "+f"(d[OFF + 93]), "+f"(d[OFF + 94]), "+f"(d[OFF + 95]), "+f"(d[OFF + 96]), "+f"(d[OFF + 97]), "+f"(d[OFF + 98]), "+f"(d[OFF + 99]), "+f"(d[OFF + 100]), "+f"(d[OFF + 101]), "+f"(d[OFF + 102]), "+f"(d[OFF + 103]), "+f"(d[OFF + 104]), "+f"(d[OFF + 105]), "+f"(d[OFF + 106]), "+f"(d[OFF + 107]), "+f"(d[OFF + 108]), "+f"(d[OFF + 109]), "+f"(d[OFF + 110]), "+f"(d[OFF + 111]), "+f"(d[OFF + 112]), "+f"(d[OFF + 113]), "+f"(d[OFF + 114]), "+f"(d[OFF + 115])
      : "l"(da), "l"(db), "r"(scale_d), "n"(TB));
}

template <int TB, int OFF = 0, int LEN>
__device__ __forceinline__ void wgmma_n192(float (&d)[LEN], uint64_t da, uint64_t db, int scale_d) {
  asm volatile(
      "{\n.reg .pred p;\nsetp.ne.b32 p, %98, 0;\n"
      "wgmma.mma_async.sync.aligned.m64n192k16.f32.bf16.bf16 "
      "{%0, %1, %2, %3, %4, %5, %6, %7, %8, %9, %10, %11, %12, %13, %14, %15, %16, %17, %18, %19, %20, %21, %22, %23, %24, %25, %26, %27, %28, %29, %30, %31, %32, %33, %34, %35, %36, %37, %38, %39, %40, %41, %42, %43, %44, %45, %46, %47, %48, %49, %50, %51, %52, %53, %54, %55, %56, %57, %58, %59, %60, %61, %62, %63, %64, %65, %66, %67, %68, %69, %70, %71, %72, %73, %74, %75, %76, %77, %78, %79, %80, %81, %82, %83, %84, %85, %86, %87, %88, %89, %90, %91, %92, %93, %94, %95}, "
      "%96, %97, p, 1, 1, 0, %99;\n}\n"
      : "+f"(d[OFF + 0]), "+f"(d[OFF + 1]), "+f"(d[OFF + 2]), "+f"(d[OFF + 3]), "+f"(d[OFF + 4]), "+f"(d[OFF + 5]), "+f"(d[OFF + 6]), "+f"(d[OFF + 7]), "+f"(d[OFF + 8]), "+f"(d[OFF + 9]), "+f"(d[OFF + 10]), "+f"(d[OFF + 11]), "+f"(d[OFF + 12]), "+f"(d[OFF + 13]), "+f"(d[OFF + 14]), "+f"(d[OFF + 15]), "+f"(d[OFF + 16]), "+f"(d[OFF + 17]), "+f"(d[OFF + 18]), "+f"(d[OFF + 19]), "+f"(d[OFF + 20]), "+f"(d[OFF + 21]), "+f"(d[OFF + 22]), "+f"(d[OFF + 23]), "+f"(d[OFF + 24]), "+f"(d[OFF + 25]), "+f"(d[OFF + 26]), "+f"(d[OFF + 27]), "+f"(d[OFF + 28]), "+f"(d[OFF + 29]), "+f"(d[OFF + 30]), "+f"(d[OFF + 31]), "+f"(d[OFF + 32]), "+f"(d[OFF + 33]), "+f"(d[OFF + 34]), "+f"(d[OFF + 35]), "+f"(d[OFF + 36]), "+f"(d[OFF + 37]), "+f"(d[OFF + 38]), "+f"(d[OFF + 39]), "+f"(d[OFF + 40]), "+f"(d[OFF + 41]), "+f"(d[OFF + 42]), "+f"(d[OFF + 43]), "+f"(d[OFF + 44]), "+f"(d[OFF + 45]), "+f"(d[OFF + 46]), "+f"(d[OFF + 47]), "+f"(d[OFF + 48]), "+f"(d[OFF + 49]), "+f"(d[OFF + 50]), "+f"(d[OFF + 51]), "+f"(d[OFF + 52]), "+f"(d[OFF + 53]), "+f"(d[OFF + 54]), "+f"(d[OFF + 55]), "+f"(d[OFF + 56]), "+f"(d[OFF + 57]), "+f"(d[OFF + 58]), "+f"(d[OFF + 59]), "+f"(d[OFF + 60]), "+f"(d[OFF + 61]), "+f"(d[OFF + 62]), "+f"(d[OFF + 63]), "+f"(d[OFF + 64]), "+f"(d[OFF + 65]), "+f"(d[OFF + 66]), "+f"(d[OFF + 67]), "+f"(d[OFF + 68]), "+f"(d[OFF + 69]), "+f"(d[OFF + 70]), "+f"(d[OFF + 71]), "+f"(d[OFF + 72]), "+f"(d[OFF + 73]), "+f"(d[OFF + 74]), "+f"(d[OFF + 75]), "+f"(d[OFF + 76]), "+f"(d[OFF + 77]), "+f"(d[OFF + 78]), "+f"(d[OFF + 79]), "+f"(d[OFF + 80]), "+f"(d[OFF + 81]), "+f"(d[OFF + 82]), "+f"(d[OFF + 83]), "+f"(d[OFF + 84]), "+f"(d[OFF + 85]), "+f"(d[OFF + 86]), "+f"(d[OFF + 87]), "+f"(d[OFF + 88]), "+f"(d[OFF + 89]), "+f"(d[OFF + 90]), "+f"(d[OFF + 91]), "+f"(d[OFF + 92]), "+f"(d[OFF + 93]), "+f"(d[OFF + 94]), "+f"(d[OFF + 95])
      : "l"(da), "l"(db), "r"(scale_d), "n"(TB));
}


__device__ __forceinline__ void release_slot(uint32_t bars, int i, int tid_wg) {
  if (i + NSLOT < KB_ALL && tid_wg == 0) mbar_arrive(bars + BAR_EMPTY + 8 * slot_of(i));
}
__device__ __forceinline__ void tma_reduce_2d(const void* map, uint32_t src, int c0, int c1) {
  asm volatile("cp.reduce.async.bulk.tensor.2d.global.shared::cta.add.tile.bulk_group [%0, {%2, %3}], [%1];" ::"l"(map), "r"(src), "r"(c0), "r"(c1) : "memory");
}
__device__ __forceinline__ float rcp(float x) { float r; asm("rcp.approx.ftz.f32 %0, %1;" : "=f"(r) : "f"(x)); return r; }
__device__ __forceinline__ uint32_t stage_addr(uint32_t base, int cw, int ch) { return cw ? base + 3 * SLOT + ch * 8192 : base + ch * SLOT + SPARE_OFF; }
__device__ __forceinline__ void tma_prefetch_2d(const void* map, int c0, int c1) {
  asm volatile("cp.async.bulk.prefetch.tensor.2d.L2.global [%0, {%1, %2}];" ::"l"(map), "r"(c0), "r"(c1) : "memory");
}
__device__ __forceinline__ void tma_prefetch_3d(const void* map, int c0, int c1, int c2) {
  asm volatile("cp.async.bulk.prefetch.tensor.3d.L2.global [%0, {%1, %2, %3}];" ::"l"(map), "r"(c0), "r"(c1), "r"(c2) : "memory");
}

__device__ __forceinline__ uint4 lds_v4(uint32_t a) { return *reinterpret_cast<const uint4*>(__cvta_shared_to_generic(a)); }
__device__ __forceinline__ void sts_v4(uint32_t a, uint4 v) { *reinterpret_cast<uint4*>(__cvta_shared_to_generic(a)) = v; }
__device__ __forceinline__ uint32_t movm_t(uint32_t a) { uint32_t d; asm volatile("movmatrix.sync.aligned.m8n8.trans.b16 %0, %1;" : "=r"(d) : "r"(a)); return d; }
__device__ __forceinline__ uint4 movm_t4(uint4 a) { return make_uint4(movm_t(a.x), movm_t(a.y), movm_t(a.z), movm_t(a.w)); }
__device__ __forceinline__ void mma_16816(float (&d)[4], uint32_t a0, uint32_t a1, uint32_t a2, uint32_t a3, uint32_t b0, uint32_t b1) {
  asm("mma.sync.aligned.m16n8k16.row.col.f32.bf16.bf16.f32 {%0,%1,%2,%3}, {%4,%5,%6,%7}, {%8,%9}, {%0,%1,%2,%3};"
               : "+f"(d[0]), "+f"(d[1]), "+f"(d[2]), "+f"(d[3]) : "r"(a0), "r"(a1), "r"(a2), "r"(a3), "r"(b0), "r"(b1));
}
template <int HI> __device__ __forceinline__ uint4 pack_rows(const float (&a)[96], int J) {
  return make_uint4(pack2(a[J + 2 * HI], a[J + 2 * HI + 1]), pack2(a[J + 4 + 2 * HI], a[J + 5 + 2 * HI]),
                    pack2(a[J + 8 + 2 * HI], a[J + 9 + 2 * HI]), pack2(a[J + 12 + 2 * HI], a[J + 13 + 2 * HI]));
}
constexpr float LOG2E = 1.4426950408889634f;
__device__ __forceinline__ void scale_logits(float& a, float& b) {
  const uint32_t d = pack2(a, b);
  const uint32_t l = pack2(bf_lo(d) * 0.17677669529663687f, bf_hi(d) * 0.17677669529663687f);
  a = bf_lo(l); b = bf_hi(l);
}

__device__ __forceinline__ void qk_tile(float (&s)[4], const uint4& q0, const uint4& q1, const uint4& k) {
  s[0] = s[1] = s[2] = s[3] = 0.f;
  mma_16816(s, q0.x, q1.x, q0.y, q1.y, k.x, k.y);
  mma_16816(s, q0.z, q1.z, q0.w, q1.w, k.z, k.w);
}
__device__ __forceinline__ void softmax_exp(float (&e)[8][2]) {
  float m[8];
#pragma unroll
  for (int r = 0; r < 8; r++) { scale_logits(e[r][0], e[r][1]); m[r] = fmaxf(e[r][0], e[r][1]); }
#pragma unroll
  for (int r = 0; r < 8; r++) m[r] = fmaxf(m[r], __shfl_xor_sync(0xffffffffu, m[r], 1));
#pragma unroll
  for (int r = 0; r < 8; r++) m[r] = fmaxf(m[r], __shfl_xor_sync(0xffffffffu, m[r], 2));
#pragma unroll
  for (int r = 0; r < 8; r++) { e[r][0] = ex2((e[r][0] - m[r]) * LOG2E); e[r][1] = ex2((e[r][1] - m[r]) * LOG2E); }
}
__device__ __forceinline__ void softmax_norm(const float (&e)[8][2], const float (&gate)[4], uint32_t (&pp)[8]) {
  float m[8];
#pragma unroll
  for (int r = 0; r < 8; r++) m[r] = e[r][0] + e[r][1];
#pragma unroll
  for (int r = 0; r < 8; r++) m[r] += __shfl_xor_sync(0xffffffffu, m[r], 1);
#pragma unroll
  for (int r = 0; r < 8; r++) m[r] += __shfl_xor_sync(0xffffffffu, m[r], 2);
#pragma unroll
  for (int r = 0; r < 8; r++) { const float f = gate[(r >> 2) * 2 + (r & 1)] * rcp(m[r]); pp[r] = pack2(e[r][0] * f, e[r][1] * f); }
}
__device__ __forceinline__ void bar_sync_dep(int id, uint32_t dep) {
  asm volatile("{\n.reg .pred p, q;\nsetp.eq.u32 p, %1, 0x7fc12345;\nbarrier.cta.red.or.aligned.pred q, %0, 256, p;\n}\n" ::"r"(id), "r"(dep) : "memory");
}
__device__ __forceinline__ void pv_group(float (&o)[2][4], uint32_t p, uint32_t msk, const uint4& vp, const uint4& vo) {
  o[0][0] = o[0][1] = o[0][2] = o[0][3] = o[1][0] = o[1][1] = o[1][2] = o[1][3] = 0.f;
  mma_16816(o[0], vp.x, vp.y, vo.x, vo.y, p & msk, p & ~msk);
  mma_16816(o[1], vp.z, vp.w, vo.z, vo.w, p & msk, p & ~msk);
}

template <int TB, int LEN>
__device__ __forceinline__ void issue256(float (&acc)[LEN], uint32_t dB, uint32_t dA, int s, int accumulate) {
  asm volatile("" : "+r"(dB), "+r"(dA));
  wgmma_fence();
#pragma unroll
  for (int k = 0; k < 4; k++) {
    const uint64_t da = make_desc(dA, s * SLOT + k * 32, 16), db = TB ? make_desc(dB, s * SLOT + k * 2048, 8192) : make_desc(dB, s * SLOT + k * 32, 16);
    if constexpr (LEN == 128) wgmma_n256<TB>(acc, da, db, k > 0 ? 1 : accumulate);
    else if constexpr (LEN == HN / 2) wgmma_n232<TB>(acc, da, db, k > 0 ? 1 : accumulate);
    else wgmma_n192<TB>(acc, da, db, k > 0 ? 1 : accumulate);
  }
  wgmma_commit();
}

template <int TB, int I0, int I1, bool FRESH, bool PEELED, int LAG, int BARID, int R0, int RN, int LEN>
__device__ __forceinline__ void mainloop256(float (&acc)[LEN], uint32_t dB, uint32_t dA, uint32_t bars, int cw, int tid_wg) {
  static_assert(RN == 0 || (R0 > I0 && R0 + 4 * RN <= I1 - LAG), "rolled section must be plain");
#pragma unroll
  for (int i = PEELED ? I0 + 1 : I0; i < I1; i++) {
    if (RN > 0 && i == R0) {
#pragma unroll 1
      for (int r = 0; r < RN; r++) {
#pragma unroll
        for (int j = 0; j < 4; j++) {
          mbar_wait(bars + BAR_FULL + 8 * slot_of(R0 + j), par_of(R0 + j) ^ (r & 1));
          issue256<TB>(acc, dB, dA, slot_of(R0 + j), 1);
          wgmma_wait<1>();
          release_slot(bars, R0 + j - 1, tid_wg);
        }
      }
    }
    if (RN > 0 && i >= R0 && i < R0 + 4 * RN) continue;
    mbar_wait(bars + BAR_FULL + 8 * slot_of(i), par_of(i));
    const bool hold = LAG > 0 && i == I1 - LAG && cw == 1;
    if (hold) { wgmma_wait<0>(); release_slot(bars, i - 1, tid_wg); bar_sync(BARID, 256); }
    issue256<TB>(acc, dB, dA, slot_of(i), (FRESH && i == I0) ? 0 : 1);
    wgmma_wait<1>();
    if (i > I0 && !hold) release_slot(bars, i - 1, tid_wg);
    if (LAG > 0 && i == I1 - 1 && cw == 0) bar_arrive(BARID, 256);
  }
  wgmma_wait<0>();
  fence_acc(acc);
  release_slot(bars, I1 - 1, tid_wg);
}

__global__ void __cluster_dims__(2, 1, 1) __launch_bounds__(384, 1)
fused_kernel(const __grid_constant__ Maps maps, const __nv_bfloat16* __restrict__ x, const __nv_bfloat16* __restrict__ gate_w, __nv_bfloat16* __restrict__ out, uint32_t zero, int xfirst) {
  extern __shared__ uint8_t smem_raw[];
  const uint32_t base = (smem_u32(smem_raw) + 1023) & ~1023u;
  const uint32_t bars = base + SM_BAR;
  const int tid = threadIdx.x;
  const int wg = __shfl_sync(0xffffffffu, tid >> 7, 0);
  const uint32_t rank = blockIdx.x & 1;
  const int bid = xfirst ? (blockIdx.x + 128) % 132 : blockIdx.x;
  const bool extra = bid >= 128;
  const int bc = bid >> 1, t_ = bc - 4;
  const int cl = bc < 4 ? (4 + bc) * 8 : t_ < 32 ? t_ : (4 + (t_ - 32) / 7) * 8 + 1 + (t_ - 32) % 7;
  const int qm = cl >> 3, qn = 2 * (cl & 7) + rank;
  const int fm = 2 * qm + rank, fn = cl & 3, half = (cl >> 2) & 1;
  const int het = extra ? (bid - 128) * 4 : fm, hs0 = extra ? 8 * HN : (cl & 7) * HN;
  const CUtensorMap* mh = het >= 8 ? &maps.him : &maps.hre;
  const CUtensorMap* mx = extra ? &maps.xX : &maps.xH;
  const uint32_t h_aoff = extra ? 24576 : 32768, h_bytes = extra ? 40960 : 16384 + HN * 128;

  if (tid == 0) {
    mbar_init(bars + BAR_FULL, 1);
    asm volatile("fence.mbarrier_init.release.cluster;" ::: "memory");
    mbar_expect_tx(bars + BAR_FULL, h_bytes);
    tma_load_2d(base, mx, bars + BAR_FULL, 0, hs0);
    tma_load_2d(base + h_aoff, mh, bars + BAR_FULL, 0, (het & 7) * 128);
  } else if (tid == 32) {
    for (int s = 0; s < NSLOT; s++) { if (s > 0) mbar_init(bars + BAR_FULL + 8 * s, 1); mbar_init(bars + BAR_EMPTY + 8 * s, 2); }
    mbar_init(bars + BAR_HFREE, 1); mbar_init(bars + BAR_QDONE, 8);
    mbar_init(bars + BAR_HSTAGED, 4); mbar_init(bars + BAR_HSTAGED + 8, 4);
    mbar_init(bars + BAR_GATE, 1);
    for (int j = 0; j < 8; j++) mbar_init(bars + BAR_STAGED + 8 * j, 4);
    mbar_init(bars + BAR_HREADY, 1); mbar_init(bars + BAR_OREADY, 1); mbar_init(bars + BAR_HXREADY, 1);
    asm volatile("fence.mbarrier_init.release.cluster;" ::: "memory");
  }
  __syncthreads();
  if (tid == 0) {
#pragma unroll
    for (int s = 1; s < NSLOT; s++) {
      const long long t0 = clock64();
      while (clock64() - t0 < START_GAP) { }
      mbar_expect_tx(bars + BAR_FULL + 8 * s, h_bytes);
      tma_load_2d(base + s * SLOT, mx, bars + BAR_FULL + 8 * s, s * 64, hs0);
      tma_load_2d(base + s * SLOT + h_aoff, mh, bars + BAR_FULL + 8 * s, s * 64, (het & 7) * 128);
    }
  }
  __syncwarp();

  if (extra) {
    const int lane = tid & 31;
    if (tid == 0) {
      for (int i = NSLOT; i < 64; i++) {
        const int s = i & 3;
        mbar_wait(bars + BAR_EMPTY + 8 * s, ((i >> 2) & 1) ^ 1);
        mbar_expect_tx(bars + BAR_FULL + 8 * s, 40960);
        tma_load_2d(base + s * SLOT, mx, bars + BAR_FULL + 8 * s, (i & 15) * 64, hs0);
        tma_load_2d(base + s * SLOT + 24576, mh, bars + BAR_FULL + 8 * s, (i & 15) * 64, ((het + (i >> 4)) & 7) * 128);
      }
    } else if (tid == 32) {
      for (int t = 0; t < 4; t++) {
        for (int j = 0; j < 6; j++) {
          if (j % 3 == 0) mbar_wait(bars + BAR_HSTAGED + 8 * (j / 3), t & 1);
          tma_store_2d(&maps.abst, base + (j >> 1) * SLOT + 40960 + (j & 1) * 8192, hs0 + (j % 3) * 64, (het + t) * 128 + (j / 3) * 64);
        }
        bulk_commit();
        bulk_wait<0>();
        mbar_arrive(bars + BAR_HFREE);
        cnt_signal(&g_cnt[(CNT_HX + ((het + t) >> 1)) * 32]);
      }
    } else if (wg > 0) {
      const int cw = wg - 1, tid_wg = tid & 127, w4 = tid_wg >> 5;
      const uint32_t dB = (base & 0x3FFFF) >> 4, dA = dB + ((24576 + cw * 8192) >> 4);
      const int mi = lane >> 3, srow = (mi & 1) * 8 + (lane & 7);
#pragma unroll 1
      for (int t = 0; t < 4; t++) {
        float acc[96];
#pragma unroll 1
        for (int r = 0; r < 4; r++) {
#pragma unroll
          for (int j = 0; j < 4; j++) {
            mbar_wait(bars + BAR_FULL + 8 * j, r & 1);
            issue256<0>(acc, dB, dA, j, r + j > 0);
            wgmma_wait<1>();
            if (r + j > 0 && tid_wg == 0) mbar_arrive(bars + BAR_EMPTY + 8 * ((j + 3) & 3));
          }
        }
        wgmma_wait<0>();
        fence_acc(acc);
        if (tid_wg == 0) mbar_arrive(bars + BAR_EMPTY + 24);
        if (t > 0) mbar_wait(bars + BAR_HFREE, (t - 1) & 1);
#pragma unroll
        for (int ch = 0; ch < 3; ch++) {
          const int j = cw * 3 + ch;
          const uint32_t buf = base + (j >> 1) * SLOT + 40960 + (j & 1) * 8192 + w4 * 2048 + srow * 128;
#pragma unroll
          for (int jj = 0; jj < 4; jj++) {
            const float* a = &acc[ch * 32 + jj * 8];
            const int cc = 2 * jj + (mi >> 1);
            stmatrix_x4(buf + ((cc ^ (srow & 7)) << 4), pack2(a[0], a[1]), pack2(a[2], a[3]), pack2(a[4], a[5]), pack2(a[6], a[7]));
          }
        }
        fence_async_smem();
        __syncwarp();
        if (lane == 0) mbar_arrive(bars + BAR_HSTAGED + 8 * cw);
      }
    }
    return;
  }

  if (wg == 0) {
    asm volatile("setmaxnreg.dec.sync.aligned.u32 %0;" ::"n"(AUX_REGS));
    const int warp = tid >> 5, lane = tid & 31;
    if (warp == 0) {
      if (lane == 0) {
        const CUtensorMap* ms = half ? &maps.sim : &maps.sre;
        uint64_t pol;
        asm volatile("createpolicy.fractional.L2::evict_first.b64 %0, 1.0;" : "=l"(pol));
        prefetch_map(&maps.xQ); prefetch_map(&maps.wqkv); prefetch_map(ms); prefetch_map(&maps.ab); prefetch_map(&maps.o); prefetch_map(&maps.wo);
        for (int i = NSLOT; i < KB_ALL; i++) {
          const int s = (int)(((i < 32 ? SLOT_TAB : SLOT_TAB_F) >> (2 * (i & 31))) & 3);
          const uint32_t full = bars + BAR_FULL + 8 * s, sb = base + s * SLOT;
          mbar_wait(bars + BAR_EMPTY + 8 * s, (((i < 32 ? PAR_TAB : PAR_TAB_F) >> (i & 31)) & 1) ^ 1);
          if (i < KB_Q0) {
            mbar_expect_tx(full, 16384 + HN * 128);
            tma_load_2d(sb, &maps.xH, full, i * 64, hs0);
            tma_load_2d(sb + 32768, mh, full, i * 64, (het & 7) * 128);
          } else if (i < KB_S0) {
            const int kb = i - KB_Q0;
            mbar_expect_tx(full, 57344);
            tma_load_3d(sb, &maps.wqkv, full, qn * 64, kb * 64, 0);
            tma_load_5d(sb + 24576 + (s == 0 ? 16384 : 0), &maps.xQ, full, kb * 64, 0, qm * 4, 0, 0);
            tma_load_5d(sb + 24576 + (s == 0 ? 0 : 16384), &maps.xQ, full, kb * 64, 0, qm * 4, 0, 1);
          } else if (i < KB_O0) {
            const int kb = i - KB_S0;
            if (kb == 0) { mbar_wait(bars + BAR_HREADY, 0); }
            mbar_expect_tx(full, 49152);
            tma_load_2d_h(sb + 32768, ms, full, kb * 64, fm * 128, pol);
            if (kb == 8 * HN / 64) { mbar_wait(bars + BAR_HXREADY, 0); }
            tma_load_2d(sb, &maps.ab, full, kb * 64, half * 1024 + fn * 256);
          } else {
            const int kb = i - KB_O0;
            mbar_expect_tx(full, 49152);
            tma_load_4d(sb, &maps.wo, full, 0, half * 64 + kb * 8, 0, fn * 4);
            if (kb == 0) { mbar_wait(bars + BAR_OREADY, 0); }
            tma_load_2d(sb + 32768, &maps.o, full, half * 512 + kb * 64, fm * 128);
          }
          if (PF_DIST > 0) {
            if (HPD > 0 && i + HPD < KB_Q0) {
              if (i + HPD == het) tma_prefetch_2d(&maps.xH, (i + HPD) * 64, hs0);
              if (((i + HPD) & 7) == (cl & 7)) tma_prefetch_2d(mh, (i + HPD) * 64, (het & 7) * 128);
            }
            const int p = i + PF_DIST;
            if (p >= KB_Q0 && p < KB_S0) { if ((p & 7) == qm) tma_prefetch_3d(&maps.wqkv, qn * 64, (p - KB_Q0) * 64, 0); }
            else if (p >= KB_S0 && p < KB_O0) { if ((p & 3) == fn) tma_prefetch_2d(ms, (p - KB_S0) * 64, fm * 128); }
            else if (p >= KB_O0 && p < KB_ALL) {
              if ((p & 7) == qm && rank == 0) tma_prefetch_4d(&maps.wo, 0, half * 64 + (p - KB_O0) * 8, 0, fn * 4);
            }
          }
        }
      }
    } else {
      const unsigned epoch = g_epoch[bid * 4 + warp];
      mbar_wait(bars + BAR_FULL + 24, 0);
      for (int r = 2 * (warp - 1); r < 16; r += 6) {
        const uint4* xr = (const uint4*)(x + (size_t)(qm * 256 + qn * 16 + r) * 1024) + lane;
        uint4 xv[8];
#pragma unroll
        for (int j = 0; j < 8; j++) xv[j] = __ldg(xr + j * 32);
        float z0 = 0.f, z1 = 0.f;
#pragma unroll
        for (int j = 0; j < 4; j++) {
          const uint4 w = __ldg((const uint4*)gate_w + j * 32 + lane);
          const float w0 = bf_lo(w.x), w1 = bf_hi(w.x), w2 = bf_lo(w.y), w3 = bf_hi(w.y), w4 = bf_lo(w.z), w5 = bf_hi(w.z), w6 = bf_lo(w.w), w7 = bf_hi(w.w);
          const uint4 a = xv[j], b = xv[4 + j];
          z0 += bf_lo(a.x) * w0 + bf_hi(a.x) * w1 + bf_lo(a.y) * w2 + bf_hi(a.y) * w3 + bf_lo(a.z) * w4 + bf_hi(a.z) * w5 + bf_lo(a.w) * w6 + bf_hi(a.w) * w7;
          z1 += bf_lo(b.x) * w0 + bf_hi(b.x) * w1 + bf_lo(b.y) * w2 + bf_hi(b.y) * w3 + bf_lo(b.z) * w4 + bf_hi(b.z) * w5 + bf_lo(b.w) * w6 + bf_hi(b.w) * w7;
        }
#pragma unroll
        for (int o = 16; o > 0; o >>= 1) { z0 += __shfl_xor_sync(0xffffffffu, z0, o); z1 += __shfl_xor_sync(0xffffffffu, z1, o); }
        if (lane == 0) {
          const uint32_t zz = pack2(z0, z1);
          const uint32_t gg = pack2(1.f / (1.f + __expf(-bf_lo(zz))), 1.f / (1.f + __expf(-bf_hi(zz))));
          *(float2*)&g_gate[qm * 256 + qn * 16 + r] = make_float2(bf_lo(gg), bf_hi(gg));
        }
      }
      if (lane == 0) cnt_signal(&g_cnt[(CNT_GATE + qm) * 32]);
      float* sgate = (float*)(smem_raw + (base - smem_u32(smem_raw)) + SM_GATE);
      if (warp == 3) {
        if (lane == 0) cnt_wait(&g_cnt[(CNT_GATE + qm) * 32], (epoch + 1) * 48);
        __syncwarp();
        ((uint4*)sgate)[lane] = ldg_cg_v4(&g_gate[qm * 256 + lane * 4]);
        ((uint4*)sgate)[32 + lane] = ldg_cg_v4(&g_gate[qm * 256 + 128 + lane * 4]);
        __syncwarp();
        if (lane == 0) { mbar_arrive(bars + BAR_GATE); }
        mbar_wait(bars + BAR_HREADY, 0);
        mbar_wait(bars + BAR_QDONE, 0);
        uint4* z = (uint4*)(out + (size_t)(fm * 128 + half * 64) * 1024 + fn * 256) + lane;
#pragma unroll 1
        for (int r = 0; r < 64; r++) { z[r * 128] = make_uint4(0u, 0u, 0u, 0u); __nanosleep(ZERO_PACE); }
        __syncwarp();
        if (lane == 0) cnt_signal(&g_cnt[(CNT_Z + fm * 4 + fn) * 32]);
      }
      if (warp == 1) {
        mbar_wait(bars + BAR_GATE, 0);
        mbar_wait(bars + BAR_QDONE, 0);
#pragma unroll
        for (int j = 0; j < 8; j++)
          g_halo[((qm * 16 + qn) * 8 + j) * 32 + (lane & 3) * 8 + (lane >> 2)] =
              lds_v4(base + (j >> 2) * SLOT + SPARE_OFF + 3 * 2048 + (j & 1) * 1024 + ((j >> 1) & 1) * 512 + lane * 16);
        __syncwarp();
        if (lane == 0) {
          cnt_signal(&g_cnt[(CNT_HALO + qm * 16 + qn) * 32]);
          if (qm > 0) cnt_wait(&g_cnt[(CNT_HALO + (qm - 1) * 16 + qn) * 32], epoch + 1);
        }
        __syncwarp();
#pragma unroll
        for (int j = 0; j < 8; j++) {
          uint4 v = make_uint4(0u, 0u, 0u, 0u);
          if (qm > 0) v = ldg_cg_v4(&g_halo[(((qm - 1) * 16 + qn) * 8 + j) * 32 + lane]);
          sts_v4(base + (3 - (j >> 2)) * SLOT + SPARE_OFF + ((j >> 1) & 1) * 2560 + (j & 1) * 1024 + (lane >> 3) * 256 + (lane & 7) * 16, v);
        }
        __syncwarp();
        const int par = lane >> 4, hh = (lane >> 3) & 1, qi = lane & 7;
        const uint32_t buf = base + (3 - par) * SLOT + SPARE_OFF + hh * 2560;
        float p[8];
#pragma unroll
        for (int w = 0; w < 8; w++) p[w] = 0.f;
#pragma unroll 1
        for (int ch = 0; ch < 4; ch++) {
          const uint4 q = lds_v4(buf + 2048 + ch * 128 + qi * 16);
          const float q0 = bf_lo(q.x), q1 = bf_hi(q.x), q2 = bf_lo(q.y), q3 = bf_hi(q.y), q4 = bf_lo(q.z), q5 = bf_hi(q.z), q6 = bf_lo(q.w), q7 = bf_hi(q.w);
          const uint32_t ka = buf + ch * 256 + (qi + 8) * 16;
#pragma unroll
          for (int w = 0; w < 8; w++) {
            const uint4 k = lds_v4(ka - w * 16);
            float t = p[w];
            t = fmaf(q0, bf_lo(k.x), t); t = fmaf(q1, bf_hi(k.x), t); t = fmaf(q2, bf_lo(k.y), t); t = fmaf(q3, bf_hi(k.y), t);
            t = fmaf(q4, bf_lo(k.z), t); t = fmaf(q5, bf_hi(k.z), t); t = fmaf(q6, bf_lo(k.w), t); t = fmaf(q7, bf_hi(k.w), t);
            p[w] = t;
          }
        }
#pragma unroll
        for (int w = 0; w < 8; w += 2) scale_logits(p[w], p[w + 1]);
        float m = p[0];
#pragma unroll
        for (int w = 1; w < 8; w++) { if (qm == 0 && w > qi) p[w] = -1e9f; m = fmaxf(m, p[w]); }
        float sum = 0.f;
#pragma unroll
        for (int w = 0; w < 8; w++) { p[w] = ex2((p[w] - m) * LOG2E); sum += p[w]; }
        const float f = sgate[2 * qi + par] * rcp(sum);
        uint2* dst = (uint2*)(g_o + (size_t)(qm * 256 + 2 * qi + par) * 1024 + qn * 64) + hh;
#pragma unroll 1
        for (int ch = 0; ch < 4; ch++) {
          const uint32_t va = buf + 1024 + ch * 256 + (qi + 8) * 16;
          float o[8];
#pragma unroll
          for (int j = 0; j < 8; j++) o[j] = 0.f;
#pragma unroll
          for (int w = 0; w < 8; w++) {
            const uint4 v = lds_v4(va - w * 16);
            o[0] = fmaf(p[w], bf_lo(v.x), o[0]); o[1] = fmaf(p[w], bf_hi(v.x), o[1]); o[2] = fmaf(p[w], bf_lo(v.y), o[2]); o[3] = fmaf(p[w], bf_hi(v.y), o[3]);
            o[4] = fmaf(p[w], bf_lo(v.z), o[4]); o[5] = fmaf(p[w], bf_hi(v.z), o[5]); o[6] = fmaf(p[w], bf_lo(v.w), o[6]); o[7] = fmaf(p[w], bf_hi(v.w), o[7]);
          }
          dst[4 * ch] = make_uint2(pack2(o[0] * f, o[2] * f), pack2(o[4] * f, o[6] * f));
          dst[4 * ch + 2] = make_uint2(pack2(o[1] * f, o[3] * f), pack2(o[5] * f, o[7] * f));
        }
        __syncwarp();
        if (lane == 0) {
          cnt_signal(&g_cnt[(CNT_O + qm * 2 + (qn >> 3)) * 32]);
          cnt_wait(&g_cnt[(CNT_O + qm * 2 + half) * 32], (epoch + 1) * 8);
          fence_async_all();
          mbar_arrive(bars + BAR_OREADY);
        }
      } else if (lane == 0) {
        const int cw = warp - 2;
        if (cw == 0) {
#pragma unroll 1
          for (int j = 0; j < 8; j++) {
            if ((j & 3) == 0) mbar_wait(bars + BAR_HSTAGED + 2 * j, 0);
            tma_store_2d(&maps.abst, base + 3 * SLOT + (j == 7 ? 0 : j) * 8192, hs0 + ((j & 3) < 3 ? (j & 3) * 64 : HN - 64), het * 128 + (j >> 2) * 64);
            bulk_commit();
            if (j == 0) { bulk_wait_read<0>(); mbar_arrive(bars + BAR_HFREE); }
            if (j < 7) __nanosleep(HST_PACE);
          }
          bulk_wait<0>();
          cnt_signal(&g_cnt[(CNT_H + (het >> 1)) * 32]);
          cnt_wait(&g_cnt[(CNT_H + half * 4 + fn) * 32], (epoch + 1) * 16);
          fence_async_all();
          mbar_arrive(bars + BAR_HREADY);
          mbar_wait(bars + BAR_QDONE, 0);
          cnt_wait(&g_cnt[(CNT_HX + half * 4 + fn) * 32], (epoch + 1) * 2);
          fence_async_all();
          mbar_arrive(bars + BAR_HXREADY);
        }
        mbar_wait(bars + BAR_QDONE, 0);
        mbar_wait(bars + BAR_OREADY, 0);
        cnt_wait(&g_cnt[(CNT_Z + fm * 4 + fn) * 32], (epoch + 1) * 2);
        fence_async_all();
#pragma unroll
        for (int ch = 0; ch < 4; ch++) {
          mbar_wait(bars + BAR_STAGED + 32 * cw + 8 * ch, 0);
          tma_reduce_2d(&maps.out, stage_addr(base, cw, ch), fn * 256 + ch * 64, fm * 128 + cw * 64);
        }
        bulk_commit();
        bulk_wait_read<0>();
      }
      if (lane == 0) g_epoch[bid * 4 + warp] = epoch + 1;
    }
  } else {
    const int cw = wg - 1, tid_wg = tid & 127, lane = tid & 31, w4 = tid_wg >> 5;
    const int g = lane >> 2, c = lane & 3;
    const uint32_t dB = (base & 0x3FFFF) >> 4, dA = dB + ((32768 + cw * 8192) >> 4);
    const int mi = lane >> 3, srow = (mi & 1) * 8 + (lane & 7);
    const bool p0 = 2 * c > g, p1 = 2 * c + 1 > g;
    const int lrow = 2 * (w4 * 32 + g) + cw;
    const float* sgate = (const float*)(smem_raw + (base - smem_u32(smem_raw)) + SM_GATE);
    {
      float acc[HN / 2];
      mainloop256<0, 0, KB_Q0, true, false, LAG_H, 1, 1, 2>(acc, dB, dA, bars, cw, tid_wg);
#pragma unroll
      for (int ch = 0; ch < 4; ch++) {
        if (ch == 3 && cw == 1) mbar_wait(bars + BAR_HFREE, 0);
        const uint32_t buf = base + 3 * SLOT + ((ch == 3 && cw == 1) ? 0 : cw * 4 + ch) * 8192 + w4 * 2048 + srow * 128;
#pragma unroll
        for (int jj = 0; jj < 4; jj++) {
          const float* a = &acc[(ch < 3 ? ch * 32 : HN / 2 - 32) + jj * 8];
          const int cc = 2 * jj + (mi >> 1);
          stmatrix_x4(buf + ((cc ^ (srow & 7)) << 4), pack2(a[0], a[1]), pack2(a[2], a[3]), pack2(a[4], a[5]), pack2(a[6], a[7]));
        }
      }
      fence_async_smem();
      __syncwarp();
      if (lane == 0) mbar_arrive(bars + BAR_HSTAGED + 8 * cw);
    }
    asm volatile("setmaxnreg.inc.sync.aligned.u32 %0;" ::"n"(CONS_REGS));
    const uint32_t xbuf = base + cw * SLOT + SPARE_OFF + lane * 16;
    const uint32_t fbuf = base + (3 - cw) * SLOT + SPARE_OFF;
    float e[8][2];
    uint4 vt[2][5];
    {
      float acc0[96], acc1[96];
      const uint32_t dQ[2] = {dB + ((24576 + cw * 16384) >> 4), dB + ((24576 + (cw ^ 1) * 16384) >> 4)};
      auto issueQ = [&](int s, int accumulate) {
        uint32_t qB = dB, qA = dQ[s == 0];
        asm volatile("" : "+r"(qB), "+r"(qA));
        wgmma_fence();
#pragma unroll
        for (int k = 0; k < 4; k++) {
          const uint64_t db = make_desc(qB, s * SLOT + k * 2048, 8192);
          wgmma_n192<1>(acc0, make_desc(qA, s * SLOT + k * 32, 16), db, k > 0 ? 1 : accumulate);
          wgmma_n192<1>(acc1, make_desc(qA, s * SLOT + 8192 + k * 32, 16), db, k > 0 ? 1 : accumulate);
        }
        wgmma_commit();
      };
      constexpr int QR0 = KB_Q0 + 3, QRN = 3;
#pragma unroll
      for (int i = KB_Q0; i < KB_S0; i++) {
        if (i == QR0) {
#pragma unroll 1
          for (int r = 0; r < QRN; r++) {
#pragma unroll
            for (int j = 0; j < 3; j++) {
              mbar_wait(bars + BAR_FULL + 8 * slot_of(QR0 + j), par_of(QR0 + j) ^ (r & 1));
              issueQ(slot_of(QR0 + j), 1);
              wgmma_wait<1>();
              release_slot(bars, QR0 + j - 1, tid_wg);
            }
          }
        }
        if (i >= QR0 && i < QR0 + 3 * QRN) continue;
        mbar_wait(bars + BAR_FULL + 8 * slot_of(i), par_of(i));
        const bool hold = LAG_Q > 0 && i == KB_S0 - LAG_Q && cw == 1;
        if (hold) { wgmma_wait<0>(); release_slot(bars, i - 1, tid_wg); bar_sync(8, 256); }
        if (CATCH_Q > 0 && i == KB_Q0 + CATCH_Q && cw == 0) bar_sync(6, 256);
        issueQ(slot_of(i), i > KB_Q0 ? 1 : 0);
        wgmma_wait<1>();
        if (i > KB_Q0 && !hold) release_slot(bars, i - 1, tid_wg);
        if (LAG_Q > 0 && i == KB_S0 - 1 && cw == 0) bar_arrive(8, 256);
        if (CATCH_Q > 0 && i == KB_Q0 + 1 && cw == 1) bar_arrive(6, 256);
      }
      mbar_wait(bars + BAR_HREADY, 0);
      wgmma_wait<0>();
      fence_acc(acc0); fence_acc(acc1);
      release_slot(bars, KB_S0 - 1, tid_wg);
      float sc[4][3][4];
      uint4 qa[2], qb[2], k0[2];
      bar_sync(2 + cw, 128);
#pragma unroll
      for (int hh = 0; hh < 2; hh++) {
        const uint4 k3 = pack_rows<1>(acc1, 32 + hh * 16);
        sts_v4(xbuf + w4 * 2048 + hh * 512, k3);
        const uint4 q0 = pack_rows<0>(acc1, hh * 16), q1 = pack_rows<1>(acc1, hh * 16);
        const uint4 k1 = pack_rows<1>(acc0, 32 + hh * 16);
        qk_tile(sc[2 + hh][2], q0, q1, k3);
        qk_tile(sc[2 + hh][1], q0, q1, pack_rows<0>(acc1, 32 + hh * 16));
        qk_tile(sc[2 + hh][0], q0, q1, k1);
        qa[hh] = pack_rows<0>(acc0, hh * 16); qb[hh] = pack_rows<1>(acc0, hh * 16);
        k0[hh] = pack_rows<0>(acc0, 32 + hh * 16);
        qk_tile(sc[hh][2], qa[hh], qb[hh], k1);
        qk_tile(sc[hh][1], qa[hh], qb[hh], k0[hh]);
      }
      bar_sync(2 + cw, 128);
#pragma unroll
      for (int hh = 0; hh < 2; hh++) {
        qk_tile(sc[hh][0], qa[hh], qb[hh], lds_v4(xbuf + ((w4 + 3) & 3) * 2048 + hh * 512));
        vt[hh][1] = pack_rows<0>(acc0, 64 + hh * 16); vt[hh][2] = pack_rows<1>(acc0, 64 + hh * 16);
        vt[hh][3] = pack_rows<0>(acc1, 64 + hh * 16); vt[hh][4] = pack_rows<1>(acc1, 64 + hh * 16);
        if (w4 == 0) {
          sts_v4(fbuf + hh * 2560 + c * 256 + (8 + g) * 16, k0[hh]);
          sts_v4(fbuf + hh * 2560 + 2048 + c * 128 + g * 16, qa[hh]);
        }
      }
#pragma unroll
      for (int u = 0; u < 4; u++) {
        e[2 * u][0] = p0 ? sc[u][0][0] : sc[u][1][0]; e[2 * u][1] = p1 ? sc[u][0][1] : sc[u][1][1];
        e[2 * u + 1][0] = p0 ? sc[u][1][2] : sc[u][2][2]; e[2 * u + 1][1] = p1 ? sc[u][1][3] : sc[u][2][3];
      }
      bar_sync_dep(5, __float_as_uint(e[0][0]) ^ __float_as_uint(e[2][0]) ^ __float_as_uint(e[1][0]) ^ __float_as_uint(e[3][0]) ^
                          __float_as_uint(e[4][0]) ^ __float_as_uint(e[5][0]) ^ __float_as_uint(e[6][0]) ^ __float_as_uint(e[7][0]));
    }
    {
      float acc[128];
#define F_ISSUE(j) do { mbar_wait(bars + BAR_FULL + 8 * slot_of(KB_S0 + (j)), par_of(KB_S0 + (j))); issue256<0>(acc, dB, dA, slot_of(KB_S0 + (j)), (j) > 0); } while (0)
#define F_RETIRE(j, dep) do { wgmma_wait<1>(); release_slot(bars, KB_S0 + (j), tid_wg + ((dep) & zero)); } while (0)
      F_ISSUE(0);
      F_ISSUE(1);
#pragma unroll
      for (int hh = 0; hh < 2; hh++) {
        sts_v4(xbuf + w4 * 2048 + 1024 + hh * 512, vt[hh][4]);
        if (w4 == 0) sts_v4(fbuf + hh * 2560 + 1024 + c * 256 + (8 + g) * 16, vt[hh][1]);
      }
#pragma unroll
      for (int t = 1; t < 5; t++) vt[0][t] = movm_t4(vt[0][t]);
      F_RETIRE(0, 0u);
      F_ISSUE(2);
      bar_sync(2 + cw, 128);
#pragma unroll
      for (int hh = 0; hh < 2; hh++) vt[hh][0] = lds_v4(xbuf + ((w4 + 3) & 3) * 2048 + 1024 + hh * 512);
#pragma unroll
      for (int t = 1; t < 5; t++) vt[1][t] = movm_t4(vt[1][t]);
      F_RETIRE(1, 0u);
      F_ISSUE(3);
      vt[0][0] = movm_t4(vt[0][0]); vt[1][0] = movm_t4(vt[1][0]);
      softmax_exp(e);
      F_RETIRE(2, __float_as_uint(e[0][0]) ^ __float_as_uint(e[1][0]) ^ __float_as_uint(e[2][0]) ^ __float_as_uint(e[3][0]) ^
                      __float_as_uint(e[4][0]) ^ __float_as_uint(e[5][0]) ^ __float_as_uint(e[6][0]) ^ __float_as_uint(e[7][0]));
      F_ISSUE(4);
      float o[4][2][2][4];
      {
        mbar_wait(bars + BAR_GATE, 0);
        const float gate4[4] = {sgate[lrow], sgate[lrow + 16], sgate[lrow + 32], sgate[lrow + 48]};
        uint32_t pp[8];
        softmax_norm(e, gate4, pp);
        F_RETIRE(3, pp[0] ^ pp[1] ^ pp[2] ^ pp[3] ^ pp[4] ^ pp[5] ^ pp[6] ^ pp[7]);
        wgmma_wait<0>();
        fence_acc(acc);
        release_slot(bars, KB_S0 + 4, tid_wg);
        const uint32_t msk = (p0 ? 0x0000FFFFu : 0u) | (p1 ? 0xFFFF0000u : 0u) | (__float_as_uint(acc[0]) & zero);
        uint32_t dep = 0;
#pragma unroll
        for (int t = 0; t < 4; t++)
#pragma unroll
          for (int hh = 0; hh < 2; hh++) {
            pv_group(o[t][hh], pp[(t >> 1) * 4 + hh * 2 + (t & 1)], msk, vt[hh][t], vt[hh][t + 1]);
            dep ^= __float_as_uint(o[t][hh][0][3]) ^ __float_as_uint(o[t][hh][1][3]);
          }
        bar_sync_dep(5, dep);
      }
      uint4* dst = (uint4*)(g_o + (size_t)(qm * 256 + 2 * (w4 * 32 + 2 * c) + cw) * 1024 + qn * 64) + g;
#pragma unroll
      for (int t = 0; t < 4; t++) {
        F_ISSUE(5 + t);
#pragma unroll
        for (int b = 0; b < 2; b++)
          if (t > 0 || w4 > 0)
            dst[(t * 16 + b * 2) * 128] = make_uint4(pack2(o[t][0][0][b], o[t][0][0][2 + b]), pack2(o[t][0][1][b], o[t][0][1][2 + b]),
                                                     pack2(o[t][1][0][b], o[t][1][0][2 + b]), pack2(o[t][1][1][b], o[t][1][1][2 + b]));
        if (t > 0) F_RETIRE(4 + t, 0u);
      }
      __syncwarp();
      if (lane == 0) mbar_arrive(bars + BAR_QDONE);
      const int lr = rank * 128 + cw * 64 + w4 * 16 + g;
      const uint32_t ff = pack2(1.f - sgate[lr], 1.f - sgate[lr + 8]) ^ (half ? 0x80008000u : 0u);
      const float f0 = bf_lo(ff), f1 = bf_hi(ff);
      mainloop256<0, KB_S0 + 8, KB_O0, true, true, LAG_S, 4, KB_S0 + 9, 5>(acc, dB, dA, bars, cw, tid_wg);
#pragma unroll
      for (int j = 0; j < 32; j++) { acc[4 * j] *= f0; acc[4 * j + 1] *= f0; acc[4 * j + 2] *= f1; acc[4 * j + 3] *= f1; }
      mainloop256<1, KB_O0, KB_ALL, false, false, LAG_F, 7, 0, 0>(acc, dB, dA, bars, cw, tid_wg);
      static_assert(LAG_F > 0 && slot_of(KB_ALL - 4) == 3, "warpgroup 1 stages in slot 3, which both warpgroups have left");
#pragma unroll
      for (int ch = 0; ch < 4; ch++) {
        const uint32_t buf = stage_addr(base, cw, ch) + w4 * 2048 + srow * 128;
#pragma unroll
        for (int jj = 0; jj < 4; jj++) {
          const float* a = &acc[ch * 32 + jj * 8];
          const int cc = 2 * jj + (mi >> 1);
          stmatrix_x4(buf + ((cc ^ (srow & 7)) << 4), pack2(a[0], a[1]), pack2(a[2], a[3]), pack2(a[4], a[5]), pack2(a[6], a[7]));
        }
        fence_async_smem();
        __syncwarp();
        if (lane == 0) mbar_arrive(bars + BAR_STAGED + 32 * cw + 8 * ch);
      }
    }
  }
}

typedef CUresult (*EncodeFn)(CUtensorMap*, CUtensorMapDataType, cuuint32_t, void*, const cuuint64_t*, const cuuint64_t*, const cuuint32_t*,
                             const cuuint32_t*, CUtensorMapInterleave, CUtensorMapSwizzle, CUtensorMapL2promotion, CUtensorMapFloatOOBfill);

void encode(EncodeFn fn, CUtensorMap* m, const void* ptr, int rank, const cuuint64_t* dims, const cuuint64_t* strides, const cuuint32_t* box) {
  const cuuint32_t es[5] = {1, 1, 1, 1, 1};
  fn(m, CU_TENSOR_MAP_DATA_TYPE_BFLOAT16, rank, const_cast<void*>(ptr), dims, strides, box, es, CU_TENSOR_MAP_INTERLEAVE_NONE,
     CU_TENSOR_MAP_SWIZZLE_128B, CU_TENSOR_MAP_L2_PROMOTION_L2_128B, CU_TENSOR_MAP_FLOAT_OOB_FILL_NONE);
}
void encode2(EncodeFn fn, CUtensorMap* m, const void* ptr, uint64_t cols, uint64_t rows, uint32_t bc, uint32_t br) {
  const cuuint64_t d[2] = {cols, rows}, s[1] = {cols * 2};
  const cuuint32_t b[2] = {bc, br};
  encode(fn, m, ptr, 2, d, s, b);
}

}

extern "C" void kernel_launch(void* const* d_in, const int* in_sizes, int n_in, void* d_out, int out_size) {
  (void)in_sizes; (void)n_in; (void)out_size;
  const __nv_bfloat16* x = (const __nv_bfloat16*)d_in[0];
  const void* wqkv = d_in[1];
  const void* wo = d_in[2];
  const void* sre = d_in[4];
  const void* sim = d_in[5];
  const void* hre = d_in[6];
  const void* him = d_in[7];
  const __nv_bfloat16* gate_w = (const __nv_bfloat16*)d_in[8];

  static EncodeFn fn = nullptr;
  static void* ab = nullptr;
  static void* o = nullptr;
  static int xfirst = 0;
  if (!fn) {
    cudaDriverEntryPointQueryResult st;
    cudaGetDriverEntryPoint("cuTensorMapEncodeTiled", (void**)&fn, cudaEnableDefault, &st);
    cudaGetSymbolAddress(&ab, g_ab);
    cudaGetSymbolAddress(&o, g_o);
    cudaFuncSetAttribute(fused_kernel, cudaFuncAttributeMaxDynamicSharedMemorySize, SMEM_BYTES);
    int dev = 0, sms = 0;
    cudaGetDevice(&dev);
    cudaDeviceGetAttribute(&sms, cudaDevAttrMultiProcessorCount, dev);
    xfirst = sms < 132;
  }
  Maps maps;
  encode2(fn, &maps.xH, x, 1024, 2048, 64, HN);
  encode2(fn, &maps.xX, x, 1024, 2048, 64, 2048 - 8 * HN);
  encode2(fn, &maps.hre, hre, 1024, 1024, 64, 128);
  encode2(fn, &maps.him, him, 1024, 1024, 64, 128);
  {
    const cuuint64_t d[5] = {1024, 16, 32, 2, 2}, s[4] = {4096, 131072, 65536, 2048}; const cuuint32_t b[5] = {64, 16, 4, 2, 1};
    encode(fn, &maps.xQ, x, 5, d, s, b);
  }
  { const cuuint64_t d[3] = {1024, 1024, 3}, s[2] = {6144, 2048}; const cuuint32_t b[3] = {64, 64, 3}; encode(fn, &maps.wqkv, wqkv, 3, d, s, b); }
  encode2(fn, &maps.sre, sre, 2048, 2048, 64, 128);
  encode2(fn, &maps.sim, sim, 2048, 2048, 64, 128);
  encode2(fn, &maps.ab, ab, 2048, 2048, 64, 256);
  encode2(fn, &maps.abst, ab, 2048, 2048, 64, 64);
  encode2(fn, &maps.o, o, 1024, 2048, 64, 128);
  {
    const cuuint64_t d[4] = {64, 128, 8, 16}, s[3] = {16384, 2048, 128}; const cuuint32_t b[4] = {64, 8, 8, 4};
    encode(fn, &maps.wo, wo, 4, d, s, b);
  }
  encode2(fn, &maps.out, d_out, 1024, 2048, 64, 64);
  fused_kernel<<<132, 384, SMEM_BYTES>>>(maps, x, gate_w, (__nv_bfloat16*)d_out, 0u, xfirst);
}
```
